```python
import torch

def _softmax(x, axis=-1):
    return torch.softmax(x, dim=axis)
def _gelu(x):
    return torch.nn.functional.gelu(x, approximate="tanh")
def _silu(x):
    return torch.nn.functional.silu(x)
def _sigmoid(x):
    return torch.sigmoid(x)
def _layernorm(x, axis=-1, eps=1e-5):
    m = x.mean(dim=axis, keepdim=True)
    v = x.var(dim=axis, keepdim=True, unbiased=False)
    return (x - m) / torch.sqrt(v + eps)
def _scatter_add(tgt, idx, src, axis=0):
    return tgt.clone().index_add_(axis, idx, src)
def _segment_sum(src, seg, n):
    out = torch.zeros((n,) + src.shape[1:], dtype=src.dtype)
    return out.index_add_(0, seg, src)
def _pad(x, pw):
    flat = tuple(v for pair in reversed(pw) for v in pair)
    return torch.nn.functional.pad(x, flat)

kernel_name = 'gated_mix__mha_block__dense_activation_squared_relu__prompt'

def setup_inputs():

    _w = (lambda a: (lambda t: t.to(torch.bfloat16) if t.is_floating_point() else t)(torch.as_tensor(a)))
    def _A_setup():
        B, S, D, H = 1, 2048, 512, 32
        return {
            "x": _w((lambda *s: torch.randn(*s, dtype=torch.bfloat16) * 0.05)(B, S, D)),
            "wqkv": _w((lambda *s: torch.randn(*s, dtype=torch.bfloat16) * 0.8)(D, 3 * D)),
            "wo": _w((lambda *s: torch.randn(*s, dtype=torch.bfloat16) * 0.1)(D, D)),
        }
    _A_in = _A_setup()

    def _B_setup():
        B, S, D, F = 1, 2048, 512, 1376
        return {
            "x": _w((lambda *s: torch.randn(*s, dtype=torch.bfloat16) * 0.05)(B, S, D)),
            "w1": _w((lambda *s: torch.randn(*s, dtype=torch.bfloat16) * 0.1)(D, F)),
            "b1": _w((lambda *s: torch.randn(*s, dtype=torch.bfloat16) * 0.1)(F)),
            "w2": _w((lambda *s: torch.randn(*s, dtype=torch.bfloat16) * 0.1)(F, D)),
            "b2": _w((lambda *s: torch.randn(*s, dtype=torch.bfloat16) * 0.05)(D)),
        }
    _B_in = _B_setup()

    return {
        "A_x": _A_in["x"],
        "A_wqkv": _A_in["wqkv"],
        "A_wo": _A_in["wo"],
        "B_x": _B_in["x"],
        "B_w1": _B_in["w1"],
        "B_b1": _B_in["b1"],
        "B_w2": _B_in["w2"],
        "B_b2": _B_in["b2"],
        "gate_w": _w((lambda *s: torch.randn(*s, dtype=torch.bfloat16) * 0.05)(512) * 16.0),
    }

def reference(A_x, A_wqkv, A_wo, B_x, B_w1, B_b1, B_w2, B_b2, gate_w):
    def _A_ref(x, wqkv, wo):
        B, S, D = x.shape
        H = 32
        Dh = D // H
        qkv = (lambda x, *d: x.permute(*d))((x @ wqkv).reshape(B, S, 3, H, Dh), 2, 0, 3, 1, 4)
        q, k, v = qkv[0], qkv[1], qkv[2]
        scores = torch.einsum("bhqd,bhkd->bhqk", q, k) * (Dh ** -0.5)
        p = _softmax(scores, axis=-1)
        o = torch.einsum("bhqk,bhkd->bhqd", p, v)
        return (lambda x, *d: x.permute(*d))(o, 0, 2, 1, 3).reshape(B, S, D) @ wo

    def _B_ref(x, w1, b1, w2, b2):
        h = torch.einsum("bsd,df->bsf", x, w1) + b1
        zero = torch.zeros_like(h)
        r = torch.where(h > zero, h, zero)
        h = r * r
        out = torch.einsum("bsf,fd->bsd", h, w2) + b2
        return out

    x = A_x
    g = _sigmoid((x * gate_w).sum(-1, keepdims=True))
    a = _A_ref(x, A_wqkv, A_wo)
    b = _B_ref(x, B_w1, B_b1, B_w2, B_b2)
    return g * a + (1 - g) * b
```

```cpp
#include <cuda_runtime.h>
#include <cuda.h>
#include <cuda_bf16.h>
#include <cuda_fp16.h>
#include <stdint.h>

#define NMUFU 6
#define PROFILE 0

constexpr int SEQ = 2048, DM = 512, NH = 32, FF = 1376;
constexpr int NTHREADS = 640;

__device__ __align__(1024) __half        g_kv[NH * 8 * 4 * 256 * 8];
__device__ __align__(1024) __nv_bfloat16 g_h[32 * 176 * 64 * 8];
__device__ __align__(1024) __nv_bfloat16 g_o[32 * 64 * 64 * 8];
__device__ __align__(16)   float2        g_st[NH * 128];
__device__ unsigned g_cnt[(16 + 32 + 8) * 32];
__device__ unsigned g_epoch[128];
#define PROF(i)

constexpr uint32_t SM_KV = 0;
constexpr uint32_t SM_ONES = 65536;
constexpr uint32_t SM_RING = 69632;
constexpr uint32_t SM_STASH = 217088;
constexpr uint32_t SM_GATE = 227328;
constexpr uint32_t SM_STAT = 228480;
constexpr uint32_t SM_BAR = 228608;
constexpr uint32_t SM_PROF = 230400;
constexpr uint32_t SM_TOTAL = SM_PROF + (PROFILE ? 1024 : 0);
constexpr uint32_t QSTAGE = 45056, FSTAGE = 49152;
enum { B_QFULL = 0, B_QEMPTY = 8, B_KVEMPTY = 16, B_STORED = 32, B_STATS = 34, B_KVFULL = 35, B_GATE = 52, B_EVEN = 53, B_FFULL = 54, B_FEMPTY = 81, B_N = 105 };

__device__ __forceinline__ void wg_qk(uint32_t (&d)[16], uint32_t a0, uint32_t a1, uint32_t a2, uint32_t a3, uint64_t db) {
  asm volatile("{ .reg .pred p; setp.ne.b32 p, 0, 0;\n wgmma.mma_async.sync.aligned.m64n64k16.f16.f16.f16 {%0,%1,%2,%3,%4,%5,%6,%7,%8,%9,%10,%11,%12,%13,%14,%15}, {%16,%17,%18,%19}, %20, p, 1, 1, 0; }"
   : "=r"(d[0]),"=r"(d[1]),"=r"(d[2]),"=r"(d[3]),"=r"(d[4]),"=r"(d[5]),"=r"(d[6]),"=r"(d[7]),"=r"(d[8]),"=r"(d[9]),"=r"(d[10]),"=r"(d[11]),"=r"(d[12]),"=r"(d[13]),"=r"(d[14]),"=r"(d[15]) : "r"(a0),"r"(a1),"r"(a2),"r"(a3),"l"(db));
}
__device__ __forceinline__ void wg_pv(uint32_t (&d)[6], uint32_t a0, uint32_t a1, uint32_t a2, uint32_t a3, uint64_t db) {
  asm volatile("{ .reg .pred p; setp.ne.b32 p, 1, 0;\n wgmma.mma_async.sync.aligned.m64n24k16.f16.f16.f16 {%0,%1,%2,%3,%4,%5}, {%6,%7,%8,%9}, %10, p, 1, 1, 1; }"
   : "+r"(d[0]),"+r"(d[1]),"+r"(d[2]),"+r"(d[3]),"+r"(d[4]),"+r"(d[5]) : "r"(a0),"r"(a1),"r"(a2),"r"(a3),"l"(db));
}
__device__ __forceinline__ void wg_pvp(uint32_t (&d)[6], uint32_t a0, uint32_t a1, uint32_t a2, uint32_t a3, uint64_t db, int sc) {
  asm volatile("{ .reg .pred p; setp.ne.b32 p, %11, 0;\n wgmma.mma_async.sync.aligned.m64n24k16.f16.f16.f16 {%0,%1,%2,%3,%4,%5}, {%6,%7,%8,%9}, %10, p, 1, 1, 1; }"
   : "+r"(d[0]),"+r"(d[1]),"+r"(d[2]),"+r"(d[3]),"+r"(d[4]),"+r"(d[5]) : "r"(a0),"r"(a1),"r"(a2),"r"(a3),"l"(db),"r"(sc));
}
__device__ __forceinline__ void wg_n96(float (&d)[48], uint64_t da, uint64_t db, int sc) {
  asm volatile("{ .reg .pred p; setp.ne.b32 p, %50, 0;\n wgmma.mma_async.sync.aligned.m64n96k16.f32.bf16.bf16 {%0,%1,%2,%3,%4,%5,%6,%7,%8,%9,%10,%11,%12,%13,%14,%15,%16,%17,%18,%19,%20,%21,%22,%23,%24,%25,%26,%27,%28,%29,%30,%31,%32,%33,%34,%35,%36,%37,%38,%39,%40,%41,%42,%43,%44,%45,%46,%47}, %48, %49, p, 1, 1, 0, 1; }"
   : "+f"(d[0]),"+f"(d[1]),"+f"(d[2]),"+f"(d[3]),"+f"(d[4]),"+f"(d[5]),"+f"(d[6]),"+f"(d[7]),"+f"(d[8]),"+f"(d[9]),"+f"(d[10]),"+f"(d[11]),"+f"(d[12]),"+f"(d[13]),"+f"(d[14]),"+f"(d[15]),"+f"(d[16]),"+f"(d[17]),"+f"(d[18]),"+f"(d[19]),"+f"(d[20]),"+f"(d[21]),"+f"(d[22]),"+f"(d[23]),"+f"(d[24]),"+f"(d[25]),"+f"(d[26]),"+f"(d[27]),"+f"(d[28]),"+f"(d[29]),"+f"(d[30]),"+f"(d[31]),"+f"(d[32]),"+f"(d[33]),"+f"(d[34]),"+f"(d[35]),"+f"(d[36]),"+f"(d[37]),"+f"(d[38]),"+f"(d[39]),"+f"(d[40]),"+f"(d[41]),"+f"(d[42]),"+f"(d[43]),"+f"(d[44]),"+f"(d[45]),"+f"(d[46]),"+f"(d[47]) : "l"(da),"l"(db),"r"(sc));
}
__device__ __forceinline__ void wg_n128(float (&d)[64], uint64_t da, uint64_t db, int sc) {
  asm volatile("{ .reg .pred p; setp.ne.b32 p, %66, 0;\n wgmma.mma_async.sync.aligned.m64n128k16.f32.bf16.bf16 {%0,%1,%2,%3,%4,%5,%6,%7,%8,%9,%10,%11,%12,%13,%14,%15,%16,%17,%18,%19,%20,%21,%22,%23,%24,%25,%26,%27,%28,%29,%30,%31,%32,%33,%34,%35,%36,%37,%38,%39,%40,%41,%42,%43,%44,%45,%46,%47,%48,%49,%50,%51,%52,%53,%54,%55,%56,%57,%58,%59,%60,%61,%62,%63}, %64, %65, p, 1, 1, 0, 1; }"
   : "+f"(d[0]),"+f"(d[1]),"+f"(d[2]),"+f"(d[3]),"+f"(d[4]),"+f"(d[5]),"+f"(d[6]),"+f"(d[7]),"+f"(d[8]),"+f"(d[9]),"+f"(d[10]),"+f"(d[11]),"+f"(d[12]),"+f"(d[13]),"+f"(d[14]),"+f"(d[15]),"+f"(d[16]),"+f"(d[17]),"+f"(d[18]),"+f"(d[19]),"+f"(d[20]),"+f"(d[21]),"+f"(d[22]),"+f"(d[23]),"+f"(d[24]),"+f"(d[25]),"+f"(d[26]),"+f"(d[27]),"+f"(d[28]),"+f"(d[29]),"+f"(d[30]),"+f"(d[31]),"+f"(d[32]),"+f"(d[33]),"+f"(d[34]),"+f"(d[35]),"+f"(d[36]),"+f"(d[37]),"+f"(d[38]),"+f"(d[39]),"+f"(d[40]),"+f"(d[41]),"+f"(d[42]),"+f"(d[43]),"+f"(d[44]),"+f"(d[45]),"+f"(d[46]),"+f"(d[47]),"+f"(d[48]),"+f"(d[49]),"+f"(d[50]),"+f"(d[51]),"+f"(d[52]),"+f"(d[53]),"+f"(d[54]),"+f"(d[55]),"+f"(d[56]),"+f"(d[57]),"+f"(d[58]),"+f"(d[59]),"+f"(d[60]),"+f"(d[61]),"+f"(d[62]),"+f"(d[63]) : "l"(da),"l"(db),"r"(sc));
}
__device__ __forceinline__ void wg_n88(float (&d)[44], uint64_t da, uint64_t db, int sc) {
  asm volatile("{ .reg .pred p; setp.ne.b32 p, %46, 0;\n wgmma.mma_async.sync.aligned.m64n88k16.f32.bf16.bf16 {%0,%1,%2,%3,%4,%5,%6,%7,%8,%9,%10,%11,%12,%13,%14,%15,%16,%17,%18,%19,%20,%21,%22,%23,%24,%25,%26,%27,%28,%29,%30,%31,%32,%33,%34,%35,%36,%37,%38,%39,%40,%41,%42,%43}, %44, %45, p, 1, 1, 0, 1; }"
   : "+f"(d[0]),"+f"(d[1]),"+f"(d[2]),"+f"(d[3]),"+f"(d[4]),"+f"(d[5]),"+f"(d[6]),"+f"(d[7]),"+f"(d[8]),"+f"(d[9]),"+f"(d[10]),"+f"(d[11]),"+f"(d[12]),"+f"(d[13]),"+f"(d[14]),"+f"(d[15]),"+f"(d[16]),"+f"(d[17]),"+f"(d[18]),"+f"(d[19]),"+f"(d[20]),"+f"(d[21]),"+f"(d[22]),"+f"(d[23]),"+f"(d[24]),"+f"(d[25]),"+f"(d[26]),"+f"(d[27]),"+f"(d[28]),"+f"(d[29]),"+f"(d[30]),"+f"(d[31]),"+f"(d[32]),"+f"(d[33]),"+f"(d[34]),"+f"(d[35]),"+f"(d[36]),"+f"(d[37]),"+f"(d[38]),"+f"(d[39]),"+f"(d[40]),"+f"(d[41]),"+f"(d[42]),"+f"(d[43]) : "l"(da),"l"(db),"r"(sc));
}
__device__ __forceinline__ void wg_n8(float (&d)[4], uint64_t da, uint64_t db, int sc) {
  asm volatile("{ .reg .pred p; setp.ne.b32 p, %6, 0;\n wgmma.mma_async.sync.aligned.m64n8k16.f32.bf16.bf16 {%0,%1,%2,%3}, %4, %5, p, 1, 1, 0, 0; }"
   : "+f"(d[0]),"+f"(d[1]),"+f"(d[2]),"+f"(d[3]) : "l"(da),"l"(db),"r"(sc));
}
__device__ __forceinline__ void wg_fence() { asm volatile("wgmma.fence.sync.aligned;" ::: "memory"); }
__device__ __forceinline__ void wg_commit() { asm volatile("wgmma.commit_group.sync.aligned;" ::: "memory"); }
template <int N> __device__ __forceinline__ void wg_wait() { asm volatile("wgmma.wait_group.sync.aligned %0;" ::"n"(N) : "memory"); }
template <int N> __device__ __forceinline__ void pin(float (&d)[N]) {
#pragma unroll
  for (int i = 0; i < N; i++) asm volatile("" : "+f"(d[i])::"memory");
}
template <int N> __device__ __forceinline__ void pin(uint32_t (&d)[N]) {
#pragma unroll
  for (int i = 0; i < N; i++) asm volatile("" : "+r"(d[i])::"memory");
}
#define ELECT(ins) "{ .reg .pred e; elect.sync _|e, 0xffffffff;\n @e " ins " }"
template <int N> __device__ __forceinline__ void init_bars(uint32_t a, int c) {
#pragma unroll
  for (int i = 0; i < N; i++) asm volatile("mbarrier.init.shared::cta.b64 [%0], %1;" ::"r"(a + 8 * i), "r"(c) : "memory");
}
__device__ __forceinline__ bool elect() { uint32_t r; asm volatile("{ .reg .pred e; elect.sync _|e, 0xffffffff; selp.u32 %0, 1, 0, e; }" : "=r"(r)); return r; }
__device__ __forceinline__ void fence_init() { asm volatile("fence.mbarrier_init.release.cluster;" ::: "memory"); }
__device__ __forceinline__ void e_expect(uint32_t a, uint32_t b) { asm volatile(ELECT("mbarrier.arrive.expect_tx.shared::cta.b64 _, [%0], %1;") ::"r"(a), "r"(b) : "memory"); }
__device__ __forceinline__ void e_arrive(uint32_t a) { asm volatile(ELECT("mbarrier.arrive.shared::cta.b64 _, [%0];") ::"r"(a) : "memory"); }
__device__ __forceinline__ void mbar_wait(uint32_t a) {
  asm volatile(
      "{ .reg .pred p, q; .reg .u32 n;\n"
      "mbarrier.try_wait.parity.shared::cta.b64 p, [%0], 0;\n"
      "@p bra D; mov.u32 n, 0;\n"
      "W: mbarrier.try_wait.parity.shared::cta.b64 p, [%0], 0, 2000;\n"
      "add.u32 n, n, 1; setp.lt.and.u32 q, n, 0x40000, !p; @q bra W;\n"
      "D: }" ::"r"(a) : "memory");
}
__device__ __forceinline__ void e_bulk(uint32_t dst, const void* src, uint32_t bytes, uint32_t bar) {
  asm volatile(ELECT("cp.async.bulk.shared::cluster.global.mbarrier::complete_tx::bytes [%0], [%1], %2, [%3];") ::"r"(dst), "l"(src), "r"(bytes), "r"(bar) : "memory");
}
__device__ __forceinline__ void e_tma2d(uint32_t dst, const CUtensorMap* m, int c0, int c1, uint32_t bar) {
  asm volatile(ELECT("cp.async.bulk.tensor.2d.shared::cluster.global.mbarrier::complete_tx::bytes [%0], [%1, {%2, %3}], [%4];") ::"r"(dst), "l"(m), "r"(c0), "r"(c1), "r"(bar) : "memory");
}
__device__ __forceinline__ void e_tma4d(uint32_t dst, const CUtensorMap* m, int c0, int c1, int c2, int c3, uint32_t bar) {
  asm volatile(ELECT("cp.async.bulk.tensor.4d.shared::cluster.global.mbarrier::complete_tx::bytes [%0], [%1, {%2, %3, %4, %5}], [%6];") ::"r"(dst), "l"(m), "r"(c0), "r"(c1), "r"(c2), "r"(c3), "r"(bar) : "memory");
}
__device__ __forceinline__ void e_store(void* dst, uint32_t src, uint32_t bytes) {
  asm volatile(ELECT("cp.async.bulk.global.shared::cta.bulk_group [%0], [%1], %2;") ::"l"(dst), "r"(src), "r"(bytes) : "memory");
}
__device__ __forceinline__ void e_tmastore2d(const CUtensorMap* m, int c0, int c1, uint32_t src) {
  asm volatile(ELECT("cp.async.bulk.tensor.2d.global.shared::cta.bulk_group [%0, {%1, %2}], [%3];") ::"l"(m), "r"(c0), "r"(c1), "r"(src) : "memory");
}
__device__ __forceinline__ void bulk_commit() { asm volatile("cp.async.bulk.commit_group;" ::: "memory"); }
__device__ __forceinline__ void bulk_wait() { asm volatile("cp.async.bulk.wait_group 0;" ::: "memory"); }
__device__ __forceinline__ void bulk_wait_read() { asm volatile("cp.async.bulk.wait_group.read 0;" ::: "memory"); }
__device__ __forceinline__ void e_tma5d(uint32_t dst, const CUtensorMap* m, int c0, int c1, int c2, int c3, int c4, uint32_t bar) {
  asm volatile(ELECT("cp.async.bulk.tensor.5d.shared::cluster.global.mbarrier::complete_tx::bytes [%0], [%1, {%2, %3, %4, %5, %6}], [%7];") ::"r"(dst), "l"(m), "r"(c0), "r"(c1), "r"(c2), "r"(c3), "r"(c4), "r"(bar) : "memory");
}
__device__ __forceinline__ void e_prefetch(const void* p, uint32_t bytes) { asm volatile(ELECT("cp.async.bulk.prefetch.L2.global [%0], %1;") ::"l"(p), "r"(bytes) : "memory"); }
__device__ __forceinline__ void fence_async_g() { asm volatile("fence.proxy.async.global;" ::: "memory"); }
__device__ __forceinline__ void fence_async_s() { asm volatile("fence.proxy.async.shared::cta;" ::: "memory"); }
__device__ __forceinline__ void e_signal(unsigned* c) { asm volatile(ELECT("red.release.gpu.global.add.u32 [%0], 1;") ::"l"(c) : "memory"); }
template <int SLEEP> __device__ __forceinline__ void poll(const unsigned* c, unsigned target) {
  asm volatile(
      "{ .reg .pred p, q; .reg .u32 n, v; mov.u32 n, 0;\n"
      "W: ld.relaxed.gpu.global.u32 v, [%0];\n"
      "sub.u32 v, v, %1; setp.lt.s32 p, v, 0; add.u32 n, n, 1; setp.lt.and.u32 q, n, 0x800000, p;\n"
      "@q nanosleep.u32 %2;\n"
      "@q bra W;\n"
      "@p trap;\n"
      "ld.acquire.gpu.global.u32 v, [%0]; }" ::"l"(c), "r"(target), "n"(SLEEP) : "memory");
  fence_async_g();
}
__device__ __forceinline__ void poll_fast(const unsigned* c, unsigned target) {
  asm volatile(
      "{ .reg .pred p, q; .reg .u32 n, v; mov.u32 n, 0;\n"
      "W: ld.acquire.gpu.global.u32 v, [%0];\n"
      "sub.u32 v, v, %1; setp.lt.s32 p, v, 0; add.u32 n, n, 1; setp.lt.and.u32 q, n, 0x800000, p; @q bra W;\n"
      "@p trap; }" ::"l"(c), "r"(target) : "memory");
  fence_async_g();
}
__device__ __forceinline__ uint64_t mkdesc(uint32_t addr, uint32_t lbo, uint32_t sbo, uint32_t sw) {
  return (uint64_t)((addr & 0x3ffff) >> 4) | ((uint64_t)(lbo >> 4) << 16) | ((uint64_t)(sbo >> 4) << 32) | ((uint64_t)sw << 62);
}
__device__ __forceinline__ uint32_t pack_h2(float a, float b) { uint32_t r; asm("cvt.rn.f16x2.f32 %0, %1, %2;" : "=r"(r) : "f"(b), "f"(a)); return r; }
__device__ __forceinline__ uint32_t pack_b2(float a, float b) { uint32_t r; asm("cvt.rn.bf16x2.f32 %0, %1, %2;" : "=r"(r) : "f"(b), "f"(a)); return r; }
__device__ __forceinline__ uint32_t hfma2(uint32_t a, uint32_t b, uint32_t c) { uint32_t r; asm("fma.rn.f16x2 %0, %1, %2, %3;" : "=r"(r) : "r"(a), "r"(b), "r"(c)); return r; }
__device__ __forceinline__ uint32_t hadd2(uint32_t a, uint32_t b) { uint32_t r; asm("add.rn.f16x2 %0, %1, %2;" : "=r"(r) : "r"(a), "r"(b)); return r; }
__device__ __forceinline__ float ex2f(float x) { float r; asm("ex2.approx.ftz.f32 %0, %1;" : "=f"(r) : "f"(x)); return r; }

__host__ __device__ constexpr bool is_mufu(int b) { return ((b + 1) * NMUFU) / 16 != (b * NMUFU) / 16; }
constexpr float PSCALE = 1.41043f;
__device__ __forceinline__ uint32_t exp2_mufu(uint32_t x) { uint32_t r; asm("ex2.approx.f16x2 %0, %1;" : "=r"(r) : "r"(x)); return r; }
__device__ __forceinline__ uint32_t exp2_fma(uint32_t x, uint32_t negs) {
  uint32_t t = hadd2(x, 0x648E648Eu);
  uint32_t n = hfma2(t, negs, 0x454F454Fu);
  uint32_t u = hfma2(x, 0x1CA81CA8u, n);
  uint32_t v = hfma2(u, u, 0x012C012Cu);
  return __funnelshift_l(t, t, 10) + v;
}

#define ABL 0
#define PFMODE 0
#define NPRE 1
#define BURST 2
#define BURST2 4
#define PACE 0
#define HOLD 22
__host__ __device__ constexpr uint64_t mkdesc_c(uint32_t addr, uint32_t lbo, uint32_t sbo, uint32_t sw) {
  return (uint64_t)((addr & 0x3ffff) >> 4) | ((uint64_t)(lbo >> 4) << 16) | ((uint64_t)(sbo >> 4) << 32) | ((uint64_t)sw << 62);
}
constexpr uint32_t mufu_mask() { uint32_t m = 0; for (int b = 0; b < 16; b++) m |= (uint32_t)is_mufu(b) << b; return m; }
constexpr uint32_t MUFU_MASK = mufu_mask();
constexpr float QS = 0.25f * 1.4426950408889634f;

template <int N> __device__ __forceinline__ void zero(float (&d)[N]) {
#pragma unroll
  for (int i = 0; i < N; i++) d[i] = 0.f;
  pin(d);
}
struct Maps { CUtensorMap x256, wqkv, out, f[6]; };
struct Params {
  const __nv_bfloat16 *x, *wqkv, *wo, *w1, *b1, *w2, *b2, *gate;
  __nv_bfloat16* o;
  uint32_t negs;
  uint64_t dtab[27][2];
  struct { int map, dst, m0, c0, m1, c1, c2, c3; } ltab[27][2];
  uint64_t kdtab[17], vdtab[16];
};

template <bool BF> __device__ __forceinline__ void mma16816(float (&d)[4], uint32_t a0, uint32_t a1, uint32_t a2, uint32_t a3, uint32_t b0, uint32_t b1) {
  if (BF) asm volatile("mma.sync.aligned.m16n8k16.row.col.f32.bf16.bf16.f32 {%0,%1,%2,%3},{%4,%5,%6,%7},{%8,%9},{%0,%1,%2,%3};"
                       : "+f"(d[0]), "+f"(d[1]), "+f"(d[2]), "+f"(d[3]) : "r"(a0), "r"(a1), "r"(a2), "r"(a3), "r"(b0), "r"(b1));
  else asm volatile("mma.sync.aligned.m16n8k16.row.col.f32.f16.f16.f32 {%0,%1,%2,%3},{%4,%5,%6,%7},{%8,%9},{%0,%1,%2,%3};"
                    : "+f"(d[0]), "+f"(d[1]), "+f"(d[2]), "+f"(d[3]) : "r"(a0), "r"(a1), "r"(a2), "r"(a3), "r"(b0), "r"(b1));
}
__device__ __forceinline__ uint32_t mtrans(uint32_t a) { uint32_t r; asm volatile("movmatrix.sync.aligned.m8n8.trans.b16 %0, %1;" : "=r"(r) : "r"(a)); return r; }
__device__ __forceinline__ void st_gpu(uint32_t* p, uint32_t v) { asm volatile("st.relaxed.gpu.global.u32 [%0], %1;" ::"l"(p), "r"(v) : "memory"); }
__device__ __forceinline__ uint32_t ldcg32(const void* p) { return __ldcg((const unsigned*)p); }

__device__ __noinline__ float score_range(int head, uint32_t q0, uint32_t q1, uint32_t q2, uint32_t q3, float qn2, float lim2) {
  const int lane = threadIdx.x & 31;
  float mx = 0.f;
  uint32_t todo[4];
#pragma unroll
  for (int i = 0; i < 4; i++) todo[i] = __ballot_sync(0xffffffffu, __ldcg(&g_st[head * 128 + i * 32 + lane]).x * qn2 > lim2);
#pragma unroll
  for (int i = 0; i < 4; i++)
  for (uint32_t m = todo[i]; m; m &= m - 1) {
    const int grp = i * 32 + __ffs(m) - 1;
    const uint32_t* kp = (const uint32_t*)g_kv + (head * 8 + (grp >> 4)) * 4096 + (grp & 15) * 64 + lane;
    float s0[4] = {0, 0, 0, 0}, s1[4] = {0, 0, 0, 0};
    mma16816<false>(s0, q0, q1, q2, q3, ldcg32(kp + 1024), ldcg32(kp + 3072));
    mma16816<false>(s1, q0, q1, q2, q3, ldcg32(kp + 1024 + 32), ldcg32(kp + 3072 + 32));
#pragma unroll
    for (int j = 0; j < 4; j++) mx = fmaxf(mx, fmaxf(fabsf(s0[j]), fabsf(s1[j])));
  }
  return __uint_as_float(__reduce_max_sync(0xffffffffu, __float_as_uint(mx)));
}
__device__ __forceinline__ void proj16(const Params& P, int row, int col, int colt, float (&c)[2][4], float (&ct)[2][4]) {
  const int lane = threadIdx.x & 31, g = lane >> 2, t = lane & 3;
  const uint32_t* xp = (const uint32_t*)P.x + (row + g) * 256 + t;
  const unsigned short* w = (const unsigned short*)P.wqkv + 2 * t * 1536 + g;
#pragma unroll
  for (int i = 0; i < 4; i++) c[0][i] = c[1][i] = ct[0][i] = ct[1][i] = 0.f;
  for (int k = 0; k < 32; k++) {
    const uint32_t a0 = xp[k * 8], a1 = xp[k * 8 + 8 * 256], a2 = xp[k * 8 + 4], a3 = xp[k * 8 + 4 + 8 * 256];
    const unsigned short* wk = w + k * 16 * 1536;
    auto wf = [&](int kk, int n) { return (uint32_t)wk[kk * 1536 + n] | ((uint32_t)wk[(kk + 1) * 1536 + n] << 16); };
    mma16816<true>(c[0], a0, a1, a2, a3, wf(0, col), wf(8, col));
    mma16816<true>(c[1], a0, a1, a2, a3, wf(0, col + 8), wf(8, col + 8));
    const uint32_t v0 = wf(0, colt), v1 = wf(0, colt + 8), v2 = wf(8, colt), v3 = wf(8, colt + 8);
    mma16816<true>(ct[0], v0, v1, v2, v3, a0, a2);
    mma16816<true>(ct[1], v0, v1, v2, v3, a1, a3);
  }
}
template <bool RECOMP>
__device__ __noinline__ void slow_rows(const Params& P, int head, int row0, uint32_t q0, uint32_t q1, uint32_t q2, uint32_t q3, uint32_t* od) {
  const int lane = threadIdx.x & 31;
  float c[2][4], ct[2][4];
  if (RECOMP) {
    proj16(P, row0, head * 16, head * 16, c, ct);
    q0 = pack_b2(c[0][0], c[0][1]); q1 = pack_b2(c[0][2], c[0][3]); q2 = pack_b2(c[1][0], c[1][1]); q3 = pack_b2(c[1][2], c[1][3]);
  }
  float m0 = -INFINITY, m1 = -INFINITY, l0 = 0.f, l1 = 0.f, o0[4] = {0, 0, 0, 0}, o1[4] = {0, 0, 0, 0};
  for (int grp = 0; grp < 128; grp++) {
    uint32_t k[4], v[4];
    float ps0 = 1.f, ps1 = 1.f;
    if (RECOMP) {
      proj16(P, grp * 16, 512 + head * 16, 1024 + head * 16, c, ct);
      k[0] = pack_b2(c[0][0], c[0][1]); k[1] = pack_b2(c[1][0], c[1][1]); k[2] = pack_b2(c[0][2], c[0][3]); k[3] = pack_b2(c[1][2], c[1][3]);
      v[0] = pack_b2(ct[0][0], ct[0][1]); v[1] = pack_b2(ct[1][0], ct[1][1]); v[2] = pack_b2(ct[0][2], ct[0][3]); v[3] = pack_b2(ct[1][2], ct[1][3]);
    } else {
      const uint32_t* kp = (const uint32_t*)g_kv + (head * 8 + (grp >> 4)) * 4096 + (grp & 15) * 64 + lane;
      k[0] = ldcg32(kp + 1024); k[1] = ldcg32(kp + 3072); k[2] = ldcg32(kp + 1024 + 32); k[3] = ldcg32(kp + 3072 + 32);
      v[0] = mtrans(ldcg32(kp)); v[1] = mtrans(ldcg32(kp + 32)); v[2] = mtrans(ldcg32(kp + 2048)); v[3] = mtrans(ldcg32(kp + 2048 + 32));
      ps0 = ((MUFU_MASK >> ((2 * grp) & 15)) & 1) ? 1.f : PSCALE; ps1 = ((MUFU_MASK >> ((2 * grp + 1) & 15)) & 1) ? 1.f : PSCALE;
    }
    float s0[4] = {0, 0, 0, 0}, s1[4] = {0, 0, 0, 0};
    mma16816<RECOMP>(s0, q0, q1, q2, q3, k[0], k[1]);
    mma16816<RECOMP>(s1, q0, q1, q2, q3, k[2], k[3]);
    if (RECOMP) {
#pragma unroll
      for (int i = 0; i < 4; i++) { s0[i] *= QS; s1[i] *= QS; }
    }
    float x0 = fmaxf(fmaxf(s0[0], s0[1]), fmaxf(s1[0], s1[1])), x1 = fmaxf(fmaxf(s0[2], s0[3]), fmaxf(s1[2], s1[3]));
    x0 = fmaxf(x0, __shfl_xor_sync(0xffffffffu, x0, 1)); x1 = fmaxf(x1, __shfl_xor_sync(0xffffffffu, x1, 1));
    x0 = fmaxf(x0, __shfl_xor_sync(0xffffffffu, x0, 2)); x1 = fmaxf(x1, __shfl_xor_sync(0xffffffffu, x1, 2));
    x0 = fmaxf(x0, m0); x1 = fmaxf(x1, m1);
    const float a0 = ex2f(m0 - x0), a1 = ex2f(m1 - x1);
    m0 = x0; m1 = x1;
    s0[0] = ex2f(s0[0] - m0); s0[1] = ex2f(s0[1] - m0); s1[0] = ex2f(s1[0] - m0); s1[1] = ex2f(s1[1] - m0);
    s0[2] = ex2f(s0[2] - m1); s0[3] = ex2f(s0[3] - m1); s1[2] = ex2f(s1[2] - m1); s1[3] = ex2f(s1[3] - m1);
    l0 = l0 * a0 + s0[0] + s0[1] + s1[0] + s1[1]; l1 = l1 * a1 + s0[2] + s0[3] + s1[2] + s1[3];
    o0[0] *= a0; o0[1] *= a0; o1[0] *= a0; o1[1] *= a0; o0[2] *= a1; o0[3] *= a1; o1[2] *= a1; o1[3] *= a1;
    uint32_t p0, p1, p2, p3;
    if (RECOMP) { p0 = pack_b2(s0[0], s0[1]); p1 = pack_b2(s0[2], s0[3]); p2 = pack_b2(s1[0], s1[1]); p3 = pack_b2(s1[2], s1[3]); }
    else { p0 = pack_h2(s0[0] * ps0, s0[1] * ps0); p1 = pack_h2(s0[2] * ps0, s0[3] * ps0); p2 = pack_h2(s1[0] * ps1, s1[1] * ps1); p3 = pack_h2(s1[2] * ps1, s1[3] * ps1); }
    mma16816<RECOMP>(o0, p0, p1, p2, p3, v[0], v[1]);
    mma16816<RECOMP>(o1, p0, p1, p2, p3, v[2], v[3]);
  }
  l0 += __shfl_xor_sync(0xffffffffu, l0, 1); l1 += __shfl_xor_sync(0xffffffffu, l1, 1);
  l0 += __shfl_xor_sync(0xffffffffu, l0, 2); l1 += __shfl_xor_sync(0xffffffffu, l1, 2);
  const float r0 = 1.f / l0, r1 = 1.f / l1;
  st_gpu(od, pack_b2(o0[0] * r0, o0[1] * r0)); st_gpu(od + 32, pack_b2(o0[2] * r1, o0[3] * r1));
  st_gpu(od + 256, pack_b2(o1[0] * r0, o1[1] * r0)); st_gpu(od + 288, pack_b2(o1[2] * r1, o1[3] * r1));
}

constexpr float SMAX = 15.3f;
__device__ __noinline__ void resolve(const Params& P, int head, int row0, uint32_t q0, uint32_t q1, uint32_t q2, uint32_t q3, float q2n, float2 st,
                                     float l0, float l1, uint32_t r0, uint32_t r1, uint32_t r2, uint32_t r3, uint32_t* od) {
  if (!(q2n <= 16777216.f && st.x <= 16777216.f && st.y < 1e30f && st.y >= 1.5e-5f)) { slow_rows<true>(P, head, row0, q0, q1, q2, q3, od); return; }
  const float lmin = fmaxf(q2n * st.x > 13.9f * 13.9f ? 128.f : 0.f, 0.0625f * rsqrtf(st.y));
  auto nonfinite = [](uint32_t r) { return (r & 0x7f80u) == 0x7f80u || (r & 0x7f800000u) == 0x7f800000u; };
  bool redo = __any_sync(0xffffffffu, !(l0 >= lmin && l1 >= lmin && l0 + l1 < 1e30f) || nonfinite(r0) || nonfinite(r1) || nonfinite(r2) || nonfinite(r3));
  if (!redo && q2n * st.x > SMAX * SMAX) redo = !(score_range(head, q0, q1, q2, q3, q2n, SMAX * SMAX) <= SMAX);
  if (redo) slow_rows<false>(P, head, row0, q0, q1, q2, q3, od);
  else { st_gpu(od, r0); st_gpu(od + 32, r1); st_gpu(od + 256, r2); st_gpu(od + 288, r3); }
}

__global__ void __launch_bounds__(NTHREADS, 1)
fused_kernel(const __grid_constant__ Maps M, const __grid_constant__ Params P) {
  extern __shared__ __align__(1024) uint8_t smem[];
  constexpr uint32_t sb = 1024;
  if ((uint32_t)__cvta_generic_to_shared(smem) != sb) __trap();
  constexpr uint32_t bar = sb + SM_BAR;
  const int wg = __shfl_sync(0xffffffffu, threadIdx.x >> 7, 0);
  const int warp = __shfl_sync(0xffffffffu, (threadIdx.x >> 5) & 3, 0);
  const int lane = threadIdx.x & 31, t = lane & 3;
  const int cta = blockIdx.x;
  const int hp = cta >> 3, qb = cta & 7;
  const int rb = cta >> 2, cb = cta & 3;
  unsigned* cnt_kv = g_cnt; unsigned* cnt_h = g_cnt + 16 * 32; unsigned* cnt_o0 = g_cnt + 48 * 32;
  auto load_qkv = [&](int kb) {
    const uint32_t st = sb + (kb % 5) * QSTAGE, fb = bar + 8 * (B_QFULL + kb);
    e_expect(fb, QSTAGE);
    e_tma4d(st + 32768, &M.wqkv, 0, kb * 64, hp, 0, fb);
    e_tma2d(st, &M.x256, kb * 64, qb * 256, fb);
  };
  auto load_kv = [&](int step) {
    const int s = step & 3;
    const __half* src = g_kv + ((2 * hp + (step > 8)) * 8 + ((qb + step - (step <= 8)) & 7)) * 8192;
    const uint32_t fb = bar + 8 * (B_KVFULL + step);
    e_expect(fb, 16384);
    e_bulk(sb + SM_KV + s * 8192, src, 8192, fb);
    e_bulk(sb + SM_KV + 32768 + s * 4096, src + 4096, 4096, fb);
    e_bulk(sb + SM_KV + 49152 + s * 4096, src + 6144, 4096, fb);
  };

  if (wg < 4) {
    if (PFMODE == 1 && threadIdx.x < 168) {
      const int i = threadIdx.x;
      const char* p = i < 96 ? (const char*)P.x + (cta * 16 + i / 6) * 1024 + 640 + (i % 6) * 64 : (const char*)P.wqkv + 320 * 3072 + cta * 4608 + (i - 96) * 64;
      asm volatile("prefetch.global.L2 [%0];" ::"l"(p));
    }
    asm volatile("bar.sync 0, 640;" ::: "memory");
    if (wg == 0 && warp == 0) { PROF(21); }
    uint32_t qa[4], qn[4];
    float qn2a, qn2b;
    {
      float acc[48];
      zero(acc);
      uint64_t da = mkdesc(sb + wg * 8192, 16, 1024, 1), db = mkdesc_c(sb + 32768, 4096, 512, 2);
#pragma unroll 1
      for (int kb = 0; kb < 8; kb++) {
        mbar_wait(bar + 8 * (B_QFULL + kb));
        if (wg == 0 && warp == 0) { PROF(22 + kb); }
        wg_fence();
#pragma unroll
        for (int k = 0; k < 4; k++) wg_n96(acc, da + k * 2, db + k * 64, 1);
        wg_commit();
        wg_wait<1>();
        if (kb > 0) e_arrive(bar + 8 * (B_QEMPTY + kb - 1));
        const int adv = kb == 4 ? -4 * (int)(QSTAGE / 16) : (int)(QSTAGE / 16);
        da += adv; db += adv;
      }
      mbar_wait(bar + 8 * (B_QEMPTY + 5)); mbar_wait(bar + 8 * (B_QEMPTY + 6));
      if (threadIdx.x < 256) {
        const uint32_t o = ((MUFU_MASK >> ((threadIdx.x >> 3) & 15)) & 1) ? 0x3C003C00u : pack_h2(1.f / PSCALE, 1.f / PSCALE);
        *(uint4*)(smem + SM_ONES + threadIdx.x * 16) = make_uint4(o, o, o, o);
      }
      wg_wait<0>(); pin(acc);
      e_arrive(bar + 8 * (B_QEMPTY + 7));
      if (wg == 0 && warp == 0) { PROF(1); }
      const int kblk = (wg & 1) * 8 + warp * 2;
      const float vs0 = ((MUFU_MASK >> kblk) & 1) ? 1.f : 1.f / PSCALE, vs1 = ((MUFU_MASK >> (kblk + 1)) & 1) ? 1.f : 1.f / PSCALE;
      uint32_t* kvd = (uint32_t*)(smem + SM_KV) + (wg * 64 + warp * 16) * 4 + lane;
      uint32_t kf[2][4], vf[2][4];
#pragma unroll
      for (int hh = 0; hh < 2; hh++) {
        const float* k = acc + 16 + 8 * hh; const float* v = acc + 32 + 8 * hh;
        const int s = 1 - hh;
#pragma unroll
        for (int i = 0; i < 4; i++) { kf[hh][i] = pack_h2(k[2 * i], k[2 * i + 1]); const float vs = (i & 1) ? vs1 : vs0; vf[hh][i] = pack_h2(v[2 * i] * vs, v[2 * i + 1] * vs); }
        kvd[s * 2048 + 1024] = kf[hh][0]; kvd[s * 2048 + 1024 + 32] = kf[hh][1]; kvd[s * 1024 + 12288] = kf[hh][2]; kvd[s * 1024 + 12288 + 32] = kf[hh][3];
        kvd[s * 2048] = vf[hh][0]; kvd[s * 2048 + 32] = vf[hh][1]; kvd[s * 1024 + 8192] = vf[hh][2]; kvd[s * 1024 + 8192 + 32] = vf[hh][3];
      }
      fence_async_s();
      asm volatile("bar.arrive 1, 544;" ::: "memory");
#pragma unroll
      for (int i = 0; i < 4; i++) { qn[i] = pack_h2(acc[2 * i] * QS, acc[2 * i + 1] * QS); qa[i] = pack_h2(acc[8 + 2 * i] * QS, acc[8 + 2 * i + 1] * QS); }
      auto norm2max = [&](const uint32_t (&f)[4]) {
        float c0[4] = {0, 0, 0, 0}, c1[4] = {0, 0, 0, 0};
        mma16816<false>(c0, f[0], f[1], f[2], f[3], f[0], f[2]);
        mma16816<false>(c1, f[0], f[1], f[2], f[3], f[1], f[3]);
        return __int_as_float(__reduce_max_sync(0xffffffffu, max(max(__float_as_int(c0[0]), __float_as_int(c0[1])), max(__float_as_int(c1[2]), __float_as_int(c1[3])))));
      };
      qn2a = norm2max(qn); qn2b = norm2max(qa);
#pragma unroll
      for (int hh = 0; hh < 2; hh++) {
        const float kn = norm2max(kf[hh]), vn = norm2max(vf[hh]);
        if (lane == 0) g_st[(2 * hp + hh) * 128 + qb * 16 + wg * 4 + warp] = make_float2(kn, vn);
      }
      __syncwarp();
      e_arrive(bar + 8 * B_STATS);
      asm volatile("bar.sync 3, 512;" ::: "memory");
    }
    const uint32_t negs = P.negs;
    float o[10];
    uint32_t oh[6] = {0, 0, 0, 0, 0, 0};
    uint32_t sA[16], sB[16];
    pin(oh);
    if (wg == 0 && warp == 0) { PROF(4); }
    wg_fence();
    wg_qk(sA, qa[0], qa[1], qa[2], qa[3], P.kdtab[0]); wg_commit();
    wg_wait<0>(); pin(sA);
#define HALFSTEP(SC, SN, KD, VD, B0, KEEP)                                                                  \
    wg_fence();                                                                                             \
    wg_qk(SN, qa[0], qa[1], qa[2], qa[3], KD);                                                              \
    _Pragma("unroll") for (int j = 0; j < 4; j += 2) {                                                      \
      uint32_t p[8];                                                                                        \
      _Pragma("unroll") for (int i = 0; i < 8; i++)                                                         \
        p[i] = is_mufu((B0) + 2 * j + i / 2) ? exp2_mufu(SC[4 * j + i]) : exp2_fma(SC[4 * j + i], negs);    \
      wg_fence();                                                                                           \
      wg_pvp(oh, p[0], p[1], p[2], p[3], (VD) + j * 16, j ? 1 : (KEEP));                                    \
      wg_pv(oh, p[4], p[5], p[6], p[7], (VD) + j * 16 + 16);                                                \
    }                                                                                                       \
    wg_commit();                                                                                            \
    wg_wait<0>(); pin(SN);
    uint32_t flags = 0xAB55u | (0x0101u << 16) | (0x10000u << (wg * 4 + warp));
#pragma unroll 1
    for (int step = 0; step < 16; step++) {
      const int fold = flags & 1;
      const uint64_t kd = P.kdtab[step], vd = P.vdtab[step];
      HALFSTEP(sA, sB, kd + 64, vd, 0, fold)
      HALFSTEP(sB, sA, kd + 128, vd + 64, 8, 1)
      HALFSTEP(sA, sB, kd + 192, vd + 128, 0, 1)
      mbar_wait(bar + 8 * (B_KVFULL + 1 + step));
      if (flags & 0x10000) {
        if (step == wg * 4 + warp && step >= 1 && step <= 12) { mbar_wait(bar + 8 * (B_KVEMPTY + step - 1)); load_kv(step + 3); }
        if ((step & 7) == 0) {
#pragma unroll
          for (int i = 0; i < 4; i++) { const uint32_t x = qa[i]; qa[i] = qn[i]; qn[i] = x; }
        }
      }
      HALFSTEP(sB, sA, P.kdtab[step + 1], vd + 192, 8, 1)
      e_arrive(bar + 8 * (B_KVEMPTY + step));
      flags >>= 1;
      if (!fold) continue;
      pin(oh);
      uint4* stash = (uint4*)(smem + SM_STASH) + threadIdx.x;
      uint32_t* stashl = (uint32_t*)(smem + SM_STASH + 8192) + threadIdx.x;
      if (step == 0) {
        *stash = make_uint4(oh[0], oh[1], oh[2], oh[3]); *stashl = __byte_perm(oh[4], oh[5], 0x5410);
#pragma unroll
        for (int i = 0; i < 10; i++) o[i] = 0.f;
        continue;
      }
#pragma unroll
      for (int i = 0; i < 4; i++) { const float2 f = __half22float2(*(const __half2*)&oh[i]); o[2 * i] += f.x; o[2 * i + 1] += f.y; }
      o[8] += __low2float(*(const __half2*)&oh[4]); o[9] += __low2float(*(const __half2*)&oh[5]);
      if (step != 8 && step != 15) continue;
      const int odd = step == 15;
      float4 th;
      asm volatile("ld.shared.v4.f32 {%0, %1, %2, %3}, [%4];" : "=f"(th.x), "=f"(th.y), "=f"(th.z), "=f"(th.w) : "r"(sb + SM_STAT + odd * 16) : "memory");
      uint32_t* od = (uint32_t*)P.o + (((qb * 4 + wg) * 64 + odd * 32 + hp * 2) * 64 + warp * 16) * 4 + lane;
      float i0, i1;
      asm("rcp.approx.ftz.f32 %0, %1;" : "=f"(i0) : "f"(o[8])); asm("rcp.approx.ftz.f32 %0, %1;" : "=f"(i1) : "f"(o[9]));
      const uint32_t r0 = pack_b2(o[0] * i0, o[1] * i0), r1 = pack_b2(o[2] * i1, o[3] * i1), r2 = pack_b2(o[4] * i0, o[5] * i0), r3 = pack_b2(o[6] * i1, o[7] * i1);
      if (__any_sync(0xffffffffu, !(qn2a <= th.x && qn2b <= th.w && o[8] >= th.y && o[9] >= th.y && o[8] <= th.z && o[9] <= th.z))) {
        resolve(P, 2 * hp + odd, qb * 256 + wg * 64 + warp * 16, odd ? qa[0] : qn[0], odd ? qa[1] : qn[1], odd ? qa[2] : qn[2], odd ? qa[3] : qn[3],
                qn2a, ((const float2*)(smem + SM_STAT + 32))[odd], o[8], o[9], r0, r1, r2, r3, od);
        if (qn2b > th.w && th.w > 0.f && qn2b <= 16777216.f && score_range(2 * hp + 1, qa[0], qa[1], qa[2], qa[3], qn2b, SMAX * SMAX) <= SMAX) qn2b = th.w;
      } else { st_gpu(od, r0); st_gpu(od + 32, r1); st_gpu(od + 256, r2); st_gpu(od + 288, r3); }
      if (odd) break;
      qn2a = qn2b;
      {
        uint32_t* on = od + 32 * 256;
        on[0] = on[32] = on[256] = on[288] = 0xffffffffu;
        __syncwarp();
        e_arrive(bar + 8 * B_STORED);
      }
      if (wg == 0 && warp == 0) { PROF(5); }
      { const uint4 a = *stash; const uint32_t l = *stashl; oh[0] = a.x; oh[1] = a.y; oh[2] = a.z; oh[3] = a.w; oh[4] = l & 0xffff; oh[5] = l >> 16; }
      pin(oh);
#pragma unroll
      for (int i = 0; i < 10; i++) o[i] = 0.f;
    }
    {
      if (warp == 0) { PROF(48 + wg); }
      mbar_wait(bar + 8 * B_EVEN);
      const uint4* src = (const uint4*)(P.o + (rb * 64 + 32) * 512) + threadIdx.x;
      uint4 v[4];
      int n = 0;
#pragma unroll
      for (int j = 0; j < 4; j++) asm volatile("ld.relaxed.gpu.global.v4.u32 {%0, %1, %2, %3}, [%4];" : "=r"(v[j].x), "=r"(v[j].y), "=r"(v[j].z), "=r"(v[j].w) : "l"(src + j * 512) : "memory");
#pragma unroll
      for (int j = 0; j < 4; j++) {
        while ((v[j].x == 0xffffffffu || v[j].y == 0xffffffffu || v[j].z == 0xffffffffu || v[j].w == 0xffffffffu) && ++n < (1 << 22))
          asm volatile("ld.relaxed.gpu.global.v4.u32 {%0, %1, %2, %3}, [%4];" : "=r"(v[j].x), "=r"(v[j].y), "=r"(v[j].z), "=r"(v[j].w) : "l"(src + j * 512) : "memory");
        __syncwarp();
        if (j == 0) mbar_wait(bar + 8 * (B_KVEMPTY + 15));
        *((uint4*)(smem + SM_KV) + j * 512 + threadIdx.x) = v[j];
        if (j & 1) { fence_async_s(); __syncwarp(); e_arrive(bar + 8 * (B_FFULL + 25 + (j >> 1))); }
      }
      if (wg == 0 && warp == 0) { PROF(13); }
    }
  } else {
    if (warp == 0) {
      PROF(0);
      if (elect()) init_bars<8>(bar + 8 * B_QFULL, 1);
      fence_init();
      __syncwarp();
#pragma unroll
      for (int kb = 0; kb < NPRE; kb++) load_qkv(kb);
      PROF(19);
    } else if (elect()) {
      if (warp == 1) {
        init_bars<B_KVFULL - B_QEMPTY>(bar + 8 * B_QEMPTY, 16); init_bars<B_FFULL - B_KVFULL>(bar + 8 * B_KVFULL, 1);
        asm volatile("mbarrier.arrive.shared::cta.b64 _, [%0]; mbarrier.arrive.shared::cta.b64 _, [%1];" ::"r"(bar + 8 * (B_KVFULL + 1)), "r"(bar + 8 * (B_KVFULL + 16)) : "memory");
      } else if (warp == 2) { init_bars<25>(bar + 8 * B_FFULL, 2); init_bars<2>(bar + 8 * (B_FFULL + 25), 17); }
      else init_bars<24>(bar + 8 * B_FEMPTY, 4);
      fence_init();
    }
    __syncwarp();
    asm volatile("bar.sync 0, 640;" ::: "memory");
    if (warp == 0) {
#pragma unroll
      for (int kb = NPRE; kb < 5; kb++) load_qkv(kb);
      PROF(20);
    }
    const unsigned epoch1 = g_epoch[cta] + 1;
    auto issue = [&](int j, int w) {
      const auto& e = P.ltab[j][w];
      e_expect(bar + 8 * (B_FFULL + j), 16384 << w);
      e_tma5d(e.dst, (const CUtensorMap*)((const char*)M.f + e.map), cb * e.m0 + e.c0, rb * e.m1 + e.c1, e.c2, e.c3, 0, bar + 8 * (B_FFULL + j));
    };
    int lim = (warp >> 1) ? 24 : 9;
    auto release = [&](int j) {
      e_arrive(bar + 8 * (B_FEMPTY + j));
      if (((j ^ warp) & 1) == 0 && j < lim) { mbar_wait(bar + 8 * (B_FEMPTY + j)); issue(j + 3, warp >> 1); }
    };
    if (warp == 0) {
      e_expect(bar + 8 * B_GATE, 1024);
      e_bulk(sb + SM_GATE, P.gate, 1024, bar + 8 * B_GATE);
#pragma unroll 1
      for (int kb = 5; kb < 8; kb++) { mbar_wait(bar + 8 * (B_QEMPTY + kb - 5)); load_qkv(kb); }
      e_prefetch((const char*)P.w1 + cta * 11008, 11008); e_prefetch((const char*)P.w2 + cta * 11008, 11008); e_prefetch((const char*)P.wo + cta * 4096, 4096);
      mbar_wait(bar + 8 * (B_QEMPTY + 3)); mbar_wait(bar + 8 * (B_QEMPTY + 4));
      issue(0, 0); issue(0, 1);
    } else if (warp == 1) {
      __half* dst = g_kv + (2 * hp * 8 + qb) * 8192;
      asm volatile("bar.sync 1, 544;" ::: "memory");
      e_store(dst, sb + SM_KV + 8192, 8192); e_store(dst + 4096, sb + SM_KV + 32768 + 4096, 4096); e_store(dst + 6144, sb + SM_KV + 49152 + 4096, 4096);
      dst += 8 * 8192;
      e_store(dst, sb + SM_KV, 8192); e_store(dst + 4096, sb + SM_KV + 32768, 4096); e_store(dst + 6144, sb + SM_KV + 49152, 4096);
      bulk_commit();
      mbar_wait(bar + 8 * B_STATS);
      bulk_wait();
      e_signal(cnt_kv + hp * 32);
      PROF(2);
      poll_fast(cnt_kv + hp * 32, epoch1 * 8);
      PROF(3);
      load_kv(2);
      uint32_t m[4];
#pragma unroll
      for (int hh = 0; hh < 2; hh++) {
        const uint4 a = __ldcg((const uint4*)(g_st + (2 * hp + hh) * 128) + lane), b = __ldcg((const uint4*)(g_st + (2 * hp + hh) * 128) + 32 + lane);
        m[2 * hh] = __reduce_max_sync(0xffffffffu, max(max(a.x, a.z), max(b.x, b.z)));
        m[2 * hh + 1] = __reduce_max_sync(0xffffffffu, max(max(a.y, a.w), max(b.y, b.w)));
      }
      if (lane == 0) {
        float tq[2], lo[2], hi[2];
#pragma unroll
        for (int hh = 0; hh < 2; hh++) {
          const float k2 = __uint_as_float(m[2 * hh]), v2 = __uint_as_float(m[2 * hh + 1]), rv = rsqrtf(v2);
          tq[hh] = (k2 <= 16777216.f && v2 < 1e30f && v2 >= 1.5e-5f) ? fminf(0.999f * SMAX * SMAX / k2, 16777216.f) : -1.f;
          lo[hh] = fmaxf(128.f, 0.0625f * rv); hi[hh] = 60000.f * fminf(rv, 1.f);
        }
        float4* sp = (float4*)(smem + SM_STAT);
        sp[0] = make_float4(tq[0], lo[0], hi[0], tq[1]); sp[1] = make_float4(tq[1], lo[1], hi[1], INFINITY);
        *(uint4*)(sp + 2) = make_uint4(m[0], m[1], m[2], m[3]);
      }
      __syncwarp();
      load_kv(3);
#pragma unroll 1
      for (int j = 2; j < 6; j++) issue(j >> 1, j & 1);
      PROF(18);
    }
    float s0, s1;
    auto h_store = [&](const float* acc, int col8, int nblk) {
      const uint32_t* b1p = (const uint32_t*)P.b1 + col8 * 4 + t;
      uint32_t* hd = (uint32_t*)g_h + ((rb * 176 + col8) * 64 + warp * 16) * 4 + lane;
#pragma unroll
      for (int j = 0; j < nblk; j++) {
        const uint32_t bb = __ldg(b1p + j * 4);
        const float b0 = __uint_as_float(bb << 16), b1 = __uint_as_float(bb & 0xffff0000u);
        uint32_t r0, r1;
        asm("cvt.rn.relu.bf16x2.f32 %0, %1, %2;" : "=r"(r0) : "f"((acc[4 * j + 1] + b1) * s0), "f"((acc[4 * j] + b0) * s0));
        asm("cvt.rn.relu.bf16x2.f32 %0, %1, %2;" : "=r"(r1) : "f"((acc[4 * j + 3] + b1) * s1), "f"((acc[4 * j + 2] + b0) * s1));
        asm("mul.rn.bf16x2 %0, %0, %0;" : "+r"(r0)); asm("mul.rn.bf16x2 %0, %0, %0;" : "+r"(r1));
        hd[j * 256] = r0; hd[j * 256 + 32] = r1;
      }
    };
    {
      float a2[44], gz[4];
      zero(a2); zero(gz);
      mbar_wait(bar + 8 * B_GATE);
#pragma unroll 1
      for (int i = 0; i < 4; i++) {
        const uint64_t da = P.dtab[i][0], db = P.dtab[i][1], dg = mkdesc_c(sb + SM_GATE, 16, 128, 0) + i * 16;
        mbar_wait(bar + 8 * (B_FFULL + i));
        wg_fence();
#pragma unroll
        for (int k = 0; k < (ABL & 1 ? 1 : 8); k++) { wg_n88(a2, da + (k >> 2) * 512 + (k & 3) * 2, db + k * 128, 1); wg_n8(gz, da + (k >> 2) * 512 + (k & 3) * 2, dg + k * 2, 1); if (BURST < 8 && (k + 1) % BURST == 0 && k < 7) { wg_commit(); wg_wait<0>(); wg_fence(); } }
        wg_commit();
        wg_wait<0>();
        release(i);
      }
      pin(a2); pin(gz);
      s0 = __expf(-0.5f * fmaxf(__shfl_sync(0xffffffffu, gz[0], lane & ~3), -40.f));
      s1 = __expf(-0.5f * fmaxf(__shfl_sync(0xffffffffu, gz[2], lane & ~3), -40.f));
      h_store(a2, cb * 43, 11);
    }
    float acc[64];
    zero(acc);
#pragma unroll 1
    for (int i = 4; i < 12; i++) {
      const uint64_t da = P.dtab[i][0], db = P.dtab[i][1];
      mbar_wait(bar + 8 * (B_FFULL + i));
      wg_fence();
#pragma unroll
      for (int k = 0; k < (ABL & 1 ? 1 : 8); k++) { wg_n128(acc, da + (k >> 2) * 512 + (k & 3) * 2, db + k * 128, k > 0 || i != 8); if (BURST < 8 && (k + 1) % BURST == 0 && k < 7) { wg_commit(); wg_wait<0>(); wg_fence(); } }
      wg_commit();
      wg_wait<0>();
      release(i);
      if ((i & 3) == 3) { pin(acc); h_store(acc, cb * 43 + (i >> 2) * 16 - 5, 16); pin(acc); }
    }
    fence_async_g();
    asm volatile("bar.sync 2, 128;" ::: "memory");
    if (warp < 2) lim = 20;
    if (warp == 0) {
      PROF(8); e_signal(cnt_h + rb * 32); poll<200>(cnt_h + rb * 32, epoch1 * 4); PROF(9);
#pragma unroll 1
      for (int j = 12; j < 15; j++) issue(j, 0);
    }
    {
      const uint32_t* b2p = (const uint32_t*)P.b2 + cb * 64 + t;
      const float e0 = s0 * s0, e1 = s1 * s1;
#pragma unroll
      for (int j = 0; j < 16; j++) {
        const uint32_t bb = __ldg(b2p + j * 4);
        const float b0 = __uint_as_float(bb << 16), b1 = __uint_as_float(bb & 0xffff0000u);
        acc[4 * j] = b0 * e0; acc[4 * j + 1] = b1 * e0; acc[4 * j + 2] = b0 * e1; acc[4 * j + 3] = b1 * e1;
      }
      pin(acc);
    }
    int i = 12;
#pragma unroll 1
    for (int last = 0; last < 2; last++) {
      const int i0 = i, iend = last ? 27 : HOLD;
#pragma unroll 1
      do {
        const uint64_t da = P.dtab[i][0], db = P.dtab[i][1];
        mbar_wait(bar + 8 * (B_FFULL + i));
        wg_fence();
#pragma unroll
        for (int k = 0; k < (ABL & 1 ? 1 : 8); k++) {
          wg_n128(acc, da + k * 128, db + k * 128, 1);
          if ((k + 1) % BURST2 == 0) {
            wg_commit();
            if (k == BURST2 - 1) { wg_wait<1>(); if (i > i0 && i < 25) release(i - 1); }
            if (PACE && !last) wg_wait<0>();
            if (k < 7) wg_fence();
          }
        }
      } while (++i < iend);
      wg_wait<0>(); pin(acc);
      if (warp == 0) { PROF(10 + 4 * last); }
      const float g0 = __fdividef(1.f, 1.f + s0 * s0), g1 = __fdividef(1.f, 1.f + s1 * s1);
      const uint32_t ost = sb + SM_KV + 32768 + warp * 4096;
      const uint32_t orow = ost + (lane & 15) * 128;
#pragma unroll
      for (int j = 0; j < 16; j += 2) {
        const uint32_t ad = orow + (j >> 3) * 2048 + ((((j & 7) + (lane >> 4)) ^ (lane & 7)) << 4);
        asm volatile("{ .reg .pred p; setp.ne.b32 p, %5, 0; @p stmatrix.sync.aligned.m8n8.x4.shared.b16 [%0], {%1, %2, %3, %4}; }" ::"r"(ad),
                     "r"(pack_b2(acc[4 * j] * g0, acc[4 * j + 1] * g0)), "r"(pack_b2(acc[4 * j + 2] * g1, acc[4 * j + 3] * g1)),
                     "r"(pack_b2(acc[4 * j + 4] * g0, acc[4 * j + 5] * g0)), "r"(pack_b2(acc[4 * j + 6] * g1, acc[4 * j + 7] * g1)), "r"(last) : "memory");
      }
      if (last) {
        fence_async_s();
        __syncwarp();
        e_tmastore2d(&M.out, cb * 128, rb * 64 + warp * 16, ost);
        e_tmastore2d(&M.out, cb * 128 + 64, rb * 64 + warp * 16, ost + 2048);
        bulk_commit();
        break;
      }
      release(HOLD - 1);
      asm volatile("bar.sync 2, 128;" ::: "memory");
      if (warp < 2) lim = 22;
      if (warp == 0) {
        mbar_wait(bar + 8 * B_STORED); fence_async_g(); e_signal(cnt_o0 + qb * 32); poll<200>(cnt_o0 + (rb >> 2) * 32, epoch1 * 16);
        e_arrive(bar + 8 * B_EVEN);
#pragma unroll 1
        for (int j = 23; j < min(HOLD + 3, 25); j++) issue(j, 0);
        PROF(11);
      }
      mbar_wait(bar + 8 * (B_KVEMPTY + 15));
      pin(acc);
    }
    if (warp == 0 && lane == 0) g_epoch[cta] = epoch1;
    bulk_wait_read();
  }
}

typedef CUresult (*EncodeFn)(CUtensorMap*, CUtensorMapDataType, cuuint32_t, void*, const cuuint64_t*, const cuuint64_t*, const cuuint32_t*, const cuuint32_t*,
                             CUtensorMapInterleave, CUtensorMapSwizzle, CUtensorMapL2promotion, CUtensorMapFloatOOBfill);
static void mkmap(EncodeFn enc, CUtensorMap* m, const void* p, int rank, const cuuint64_t* dim, const cuuint64_t* str, const cuuint32_t* box, CUtensorMapSwizzle sw) {
  const cuuint32_t es[5] = {1, 1, 1, 1, 1};
  enc(m, CU_TENSOR_MAP_DATA_TYPE_BFLOAT16, rank, (void*)p, dim, str, box, es, CU_TENSOR_MAP_INTERLEAVE_NONE, sw, CU_TENSOR_MAP_L2_PROMOTION_L2_128B,
      CU_TENSOR_MAP_FLOAT_OOB_FILL_NONE);
}
static void map5(EncodeFn enc, CUtensorMap* m, const void* p, uint64_t cols, uint64_t rows, uint32_t boxrows, uint32_t nbox, CUtensorMapSwizzle sw) {
  const cuuint64_t dim[5] = {cols, rows, 1, 1, nbox}, str[4] = {cols * 2, cols * 2, cols * 2, 128};
  const cuuint32_t box[5] = {64, boxrows, 1, 1, nbox};
  mkmap(enc, m, p, 5, dim, str, box, sw);
}
extern "C" void kernel_launch(void* const* d_in, const int* in_sizes, int n_in, void* d_out, int out_size) {
  Params P;
  P.x = (const __nv_bfloat16*)d_in[0]; P.wqkv = (const __nv_bfloat16*)d_in[1]; P.wo = (const __nv_bfloat16*)d_in[2];
  P.w1 = (const __nv_bfloat16*)d_in[4]; P.b1 = (const __nv_bfloat16*)d_in[5]; P.w2 = (const __nv_bfloat16*)d_in[6];
  P.b2 = (const __nv_bfloat16*)d_in[7]; P.gate = (const __nv_bfloat16*)d_in[8];
  P.negs = 0x9CA89CA8u;
  for (int i = 0; i < 27; i++) {
    const int st = 1024 + SM_RING + ((i + 2) % 3) * FSTAGE;
    P.dtab[i][0] = i < 12 ? mkdesc_c(st, 16, 1024, 1) : mkdesc_c(i < 25 ? st : 1024 + SM_KV + (i - 25) * 16384, 1024, 128, 0);
    P.dtab[i][1] = mkdesc_c(st + 16384, 16384, 1024, 1);
    if (i < 12) {
      P.ltab[i][0] = {0 * 128, st, 0, (i & 3) * 128, 64, 0, 0, 0};
      P.ltab[i][1] = {1 * 128, st + 16384, 344, i < 4 ? 0 : (i >> 2) * 128 - 40, 0, (i & 3) * 128, 0, 0};
    } else if (i < 23) {
      P.ltab[i][0] = {2 * 128, st, 0, 0, 176 * 8, (i - 12) * 128, 0, 0};
      P.ltab[i][1] = {3 * 128, st + 16384, 128, 0, 0, (i - 12) * 128, 0, 0};
    } else {
      P.ltab[i][0] = {4 * 128, st, 0, 0, 64 * 8, (i - 23) * 128, 0, 0};
      P.ltab[i][1] = {5 * 128, st + 16384, 128, 0, 0, 0, (i - 23) >> 1, ((i - 23) & 1) * 8};
    }
  }
  for (int i = 0; i < 17; i++) {
    const uint32_t s = i & 3;
    P.kdtab[i] = mkdesc_c(1024 + SM_KV + s * 8192 + 4096, 49152 - 4096 - s * 4096, 128, 0);
    if (i < 16) P.vdtab[i] = mkdesc_c(1024 + SM_KV + s * 8192, 128, 32768 - s * 4096, 0);
  }
  void* fn = nullptr; cudaDriverEntryPointQueryResult qr;
  cudaGetDriverEntryPoint("cuTensorMapEncodeTiled", &fn, cudaEnableDefault, &qr);
  EncodeFn enc = (EncodeFn)fn;
  void *ph = nullptr, *po = nullptr;
  cudaGetSymbolAddress(&ph, g_h); cudaGetSymbolAddress(&po, g_o);
  P.o = (__nv_bfloat16*)po;
  Maps M;
  { const cuuint64_t dim[2] = {DM, SEQ}, str[1] = {DM * 2}; const cuuint32_t b256[2] = {64, 256}, b16[2] = {64, 16};
    mkmap(enc, &M.x256, P.x, 2, dim, str, b256, CU_TENSOR_MAP_SWIZZLE_128B); mkmap(enc, &M.out, d_out, 2, dim, str, b16, CU_TENSOR_MAP_SWIZZLE_128B); }
  {
    const cuuint64_t dim[4] = {32, DM, 16, 3}, str[3] = {3 * DM * 2, 64, DM * 2}; const cuuint32_t box[4] = {32, 64, 1, 3};
    mkmap(enc, &M.wqkv, P.wqkv, 4, dim, str, box, CU_TENSOR_MAP_SWIZZLE_64B);
  }
  map5(enc, &M.f[0], P.x, DM, SEQ, 64, 2, CU_TENSOR_MAP_SWIZZLE_128B);
  map5(enc, &M.f[1], P.w1, FF, DM, 128, 2, CU_TENSOR_MAP_SWIZZLE_128B);
  map5(enc, &M.f[2], ph, 64, 32 * 176 * 8, 128, 1, CU_TENSOR_MAP_SWIZZLE_NONE);
  map5(enc, &M.f[3], P.w2, DM, FF, 128, 2, CU_TENSOR_MAP_SWIZZLE_128B);
  map5(enc, &M.f[4], po, 64, 32 * 64 * 8, 128, 1, CU_TENSOR_MAP_SWIZZLE_NONE);
  {
    const cuuint64_t dim[5] = {DM, 16, 2, 16, 2}, str[4] = {DM * 2, 16 * DM * 2, 32 * DM * 2, 128}; const cuuint32_t box[5] = {64, 16, 1, 8, 2};
    mkmap(enc, &M.f[5], P.wo, 5, dim, str, box, CU_TENSOR_MAP_SWIZZLE_128B);
  }
  cudaFuncSetAttribute(fused_kernel, cudaFuncAttributeMaxDynamicSharedMemorySize, SM_TOTAL);
  fused_kernel<<<128, NTHREADS, SM_TOTAL, cudaStreamPerThread>>>(M, P);
}
```
